```python
import torch

def _softmax(x, axis=-1):
    return torch.softmax(x, dim=axis)
def _gelu(x):
    return torch.nn.functional.gelu(x, approximate="tanh")
def _silu(x):
    return torch.nn.functional.silu(x)
def _sigmoid(x):
    return torch.sigmoid(x)
def _layernorm(x, axis=-1, eps=1e-5):
    m = x.mean(dim=axis, keepdim=True)
    v = x.var(dim=axis, keepdim=True, unbiased=False)
    return (x - m) / torch.sqrt(v + eps)
def _scatter_add(tgt, idx, src, axis=0):
    return tgt.clone().index_add_(axis, idx, src)
def _segment_sum(src, seg, n):
    out = torch.zeros((n,) + src.shape[1:], dtype=src.dtype)
    return out.index_add_(0, seg, src)
def _pad(x, pw):
    flat = tuple(v for pair in reversed(pw) for v in pair)
    return torch.nn.functional.pad(x, flat)

kernel_name = 'standalone__groupnorm__prompt'

def setup_inputs():

    _w = (lambda a: (lambda t: t.to(torch.bfloat16) if t.is_floating_point() else t)(torch.as_tensor(a)))
    B = 1
    G = 32
    cpg = max(1, 448 // G)
    C = G * cpg
    H, W = 16, 4096
    return {
        "x": _w(abs((lambda *s: torch.randn(*s, dtype=torch.bfloat16) * 0.05)(B, C, H, W))),
        "g": _w((lambda *s: torch.randn(*s, dtype=torch.bfloat16) * 0.05)(C) + 1.0),
        "b": _w((lambda *s: torch.randn(*s, dtype=torch.bfloat16) * 0.4)(C)),
    }

def reference(x, g, b):
    G = 32
    B, C, H, W = x.shape[0], x.shape[1], x.shape[2], x.shape[3]
    xr = x.reshape(B, G, C // G, H, W)
    mu = xr.mean(axis=(2, 3, 4), keepdims=True)
    var = ((xr - mu) ** 2).mean(axis=(2, 3, 4), keepdims=True)
    xn = (xr - mu) / torch.sqrt(var + 1e-5)
    xn = xn.reshape(B, C, H, W)
    return xn * g[None, :, None, None] + b[None, :, None, None]
```

```cpp
#include <cuda_runtime.h>
#include <cuda_bf16.h>
#include <stdint.h>

namespace gn {

constexpr int G            = 32;
constexpr int CPG          = 14;
constexpr int HW           = 16 * 4096;
constexpr int GROUP_ELEMS  = CPG * HW;
constexpr int CTAS_PER_GRP = 32;
constexpr int GRPS_PER_WAVE= 4;
constexpr int NCTA         = CTAS_PER_GRP * GRPS_PER_WAVE;
constexpr int WAVES        = G / GRPS_PER_WAVE;
constexpr int SLICE_ELEMS  = GROUP_ELEMS / CTAS_PER_GRP;
constexpr int SLICE_BYTES  = SLICE_ELEMS * 2;
constexpr int ROW_ELEMS    = 4096;
constexpr int ROWS_PER_SLICE = SLICE_ELEMS / ROW_ELEMS;
constexpr int ROWS_PER_CH  = HW / ROW_ELEMS;
constexpr int THREADS      = 512;
constexpr int NWARPS       = THREADS / 32;
constexpr int STAGES       = 4;
constexpr int LOOKAHEAD    = 2;
constexpr int SMEM_BYTES   = STAGES * SLICE_BYTES + 1024;
constexpr unsigned long long EMPTY = 0ull;

__device__ unsigned long long g_slot[G][CTAS_PER_GRP];
__device__ unsigned int       g_depart[G];

__device__ __forceinline__ uint32_t smem_u32(const void* p) {
    return (uint32_t)__cvta_generic_to_shared(p);
}
__device__ __forceinline__ void mbar_init(uint32_t bar, uint32_t cnt) {
    asm volatile("mbarrier.init.shared::cta.b64 [%0], %1;" :: "r"(bar), "r"(cnt) : "memory");
}
__device__ __forceinline__ void mbar_expect_tx(uint32_t bar, uint32_t bytes) {
    asm volatile("mbarrier.arrive.expect_tx.shared::cta.b64 _, [%0], %1;" :: "r"(bar), "r"(bytes) : "memory");
}
__device__ __forceinline__ void mbar_wait(uint32_t bar, uint32_t parity) {
    asm volatile(
        "{\n"
        ".reg .pred p;\n"
        "WAIT_LOOP:\n"
        "mbarrier.try_wait.parity.shared::cta.b64 p, [%0], %1;\n"
        "@p bra WAIT_DONE;\n"
        "bra WAIT_LOOP;\n"
        "WAIT_DONE:\n"
        "}\n" :: "r"(bar), "r"(parity) : "memory");
}
__device__ __forceinline__ uint64_t policy_evict_first() {
    uint64_t pol;
    asm volatile("createpolicy.fractional.L2::evict_first.b64 %0, 1.0;" : "=l"(pol));
    return pol;
}
__device__ __forceinline__ void bulk_load(uint32_t dst, const void* src, uint32_t bytes, uint32_t bar) {
    asm volatile(
        "cp.async.bulk.shared::cluster.global.mbarrier::complete_tx::bytes.L2::cache_hint [%0], [%1], %2, [%3], %4;"
        :: "r"(dst), "l"(src), "r"(bytes), "r"(bar), "l"(policy_evict_first()) : "memory");
}

__device__ __forceinline__ void accum8(const uint4& v, float K, float& s1, float& s2) {
    const uint32_t w[4] = {v.x, v.y, v.z, v.w};
#pragma unroll
    for (int i = 0; i < 4; i++) {
        float lo = __uint_as_float(w[i] << 16) - K;
        float hi = __uint_as_float(w[i] & 0xffff0000u) - K;
        s1 += lo; s2 = fmaf(lo, lo, s2);
        s1 += hi; s2 = fmaf(hi, hi, s2);
    }
}
__device__ __forceinline__ uint32_t norm2(uint32_t w, float sc, float sh) {
    float lo = fmaf(__uint_as_float(w << 16), sc, sh);
    float hi = fmaf(__uint_as_float(w & 0xffff0000u), sc, sh);
    __nv_bfloat162 r = __floats2bfloat162_rn(lo, hi);
    return *reinterpret_cast<uint32_t*>(&r);
}

struct SmemCtl {
    uint64_t full_bar[STAGES];
    float    red[2][NWARPS];
    float    bcast[2];
    float    shiftK[WAVES];
    float    gam[WAVES][2];
    float    bet[WAVES][2];
};

__global__ void __launch_bounds__(THREADS, 1)
groupnorm_kernel(const __nv_bfloat16* __restrict__ x,
                 const __nv_bfloat16* __restrict__ gamma,
                 const __nv_bfloat16* __restrict__ beta,
                 __nv_bfloat16* __restrict__ out)
{
    extern __shared__ __align__(1024) unsigned char smem_raw[];
    unsigned char* stage_base = smem_raw;
    SmemCtl* ctl = reinterpret_cast<SmemCtl*>(smem_raw + STAGES * SLICE_BYTES);

    const int tid  = threadIdx.x;
    const int lane = tid & 31;
    const int warp = tid >> 5;
    const int cta  = blockIdx.x;
    const int gsub = cta / CTAS_PER_GRP;
    const int sidx = cta % CTAS_PER_GRP;
    const int row0 = sidx * ROWS_PER_SLICE;
    const int ch0  = row0 / ROWS_PER_CH;

    if (tid == 0) {
#pragma unroll
        for (int s = 0; s < STAGES; s++) mbar_init(smem_u32(&ctl->full_bar[s]), 1);
        asm volatile("fence.mbarrier_init.release.cluster;" ::: "memory");
    }
    if (warp == 1 && lane < WAVES) {
        const int grp = lane * GRPS_PER_WAVE + gsub;
        ctl->shiftK[lane] = __bfloat162float(x[(size_t)grp * GROUP_ELEMS]);
        const int c = grp * CPG + ch0;
        const int c1 = min(c + 1, G * CPG - 1);
        ctl->gam[lane][0] = __bfloat162float(gamma[c]);
        ctl->gam[lane][1] = __bfloat162float(gamma[c1]);
        ctl->bet[lane][0] = __bfloat162float(beta[c]);
        ctl->bet[lane][1] = __bfloat162float(beta[c1]);
    }
    __syncthreads();

    auto issue_load = [&](int w) {
        const int grp = w * GRPS_PER_WAVE + gsub;
        const __nv_bfloat16* src = x + (size_t)grp * GROUP_ELEMS + (size_t)sidx * SLICE_ELEMS;
        const int st = w % STAGES;
        const uint32_t bar = smem_u32(&ctl->full_bar[st]);
        mbar_expect_tx(bar, SLICE_BYTES);
        bulk_load(smem_u32(stage_base + st * SLICE_BYTES), src, SLICE_BYTES, bar);
    };
    if (tid == 0) {
#pragma unroll
        for (int w = 0; w < STAGES; w++) issue_load(w);
    }

    auto stats_publish = [&](int w) {
        const int grp = w * GRPS_PER_WAVE + gsub;
        const int st  = w % STAGES;
        const uint4* sbuf = reinterpret_cast<const uint4*>(stage_base + st * SLICE_BYTES);
        const float K = ctl->shiftK[w];
        mbar_wait(smem_u32(&ctl->full_bar[st]), (w / STAGES) & 1);
        float s1 = 0.f, s2 = 0.f;
#pragma unroll
        for (int r = 0; r < ROWS_PER_SLICE; r++) {
            uint4 v = sbuf[r * (ROW_ELEMS / 8) + tid];
            accum8(v, K, s1, s2);
        }
#pragma unroll
        for (int o = 16; o > 0; o >>= 1) {
            s1 += __shfl_xor_sync(0xffffffffu, s1, o);
            s2 += __shfl_xor_sync(0xffffffffu, s2, o);
        }
        if (lane == 0) { ctl->red[0][warp] = s1; ctl->red[1][warp] = s2; }
        __syncthreads();
        if (warp == 0) {
            float t1 = (lane < NWARPS) ? ctl->red[0][lane] : 0.f;
            float t2 = (lane < NWARPS) ? ctl->red[1][lane] : 0.f;
#pragma unroll
            for (int o = 16; o > 0; o >>= 1) {
                t1 += __shfl_xor_sync(0xffffffffu, t1, o);
                t2 += __shfl_xor_sync(0xffffffffu, t2, o);
            }
            if (lane == 0) {
                unsigned long long pv = ((unsigned long long)__float_as_uint(t2) << 32) | __float_as_uint(t1);
                if (pv == EMPTY) pv = 0x8000000080000000ull;
                asm volatile("st.relaxed.gpu.global.u64 [%0], %1;" :: "l"(&g_slot[grp][sidx]), "l"(pv) : "memory");
            }
        }
    };

#pragma unroll
    for (int w = 0; w < LOOKAHEAD; w++) stats_publish(w);

    for (int w = 0; w < WAVES; w++) {
        const int grp = w * GRPS_PER_WAVE + gsub;
        const int st  = w % STAGES;
        const uint4* sbuf = reinterpret_cast<const uint4*>(stage_base + st * SLICE_BYTES);

        if (w + LOOKAHEAD < WAVES) stats_publish(w + LOOKAHEAD);
        else __syncthreads();

        if (warp == 0) {
            unsigned long long sv;
            for (unsigned int it = 0; it < 100000000u; it++) {
                asm volatile("ld.relaxed.gpu.global.u64 %0, [%1];" : "=l"(sv) : "l"(&g_slot[grp][lane]) : "memory");
                if (__all_sync(0xffffffffu, sv != EMPTY)) break;
            }
            float a1 = __uint_as_float((unsigned int)sv), a2 = __uint_as_float((unsigned int)(sv >> 32));
#pragma unroll
            for (int o = 16; o > 0; o >>= 1) {
                a1 += __shfl_xor_sync(0xffffffffu, a1, o);
                a2 += __shfl_xor_sync(0xffffffffu, a2, o);
            }
            if (lane == 0) {
                const float inv_n = 1.0f / (float)GROUP_ELEMS;
                const float m   = a1 * inv_n;
                const float var = fmaxf(a2 * inv_n - m * m, 0.f);
                ctl->bcast[0] = ctl->shiftK[w] + m;
                ctl->bcast[1] = rsqrtf(var + 1e-5f);
                unsigned int d = atomicAdd(&g_depart[grp], 1u);
                if (d == CTAS_PER_GRP - 1) {
                    g_depart[grp] = 0u;
#pragma unroll 4
                    for (int i = 0; i < CTAS_PER_GRP; i++) g_slot[grp][i] = EMPTY;
                }
            }
        }
        __syncthreads();
        const float mean = ctl->bcast[0];
        const float rstd = ctl->bcast[1];
        const float sc0 = rstd * ctl->gam[w][0], sh0 = fmaf(-mean, sc0, ctl->bet[w][0]);
        const float sc1 = rstd * ctl->gam[w][1], sh1 = fmaf(-mean, sc1, ctl->bet[w][1]);

        const size_t slice_off = (size_t)grp * GROUP_ELEMS + (size_t)sidx * SLICE_ELEMS;
        uint4* dst = reinterpret_cast<uint4*>(out + slice_off);
#pragma unroll
        for (int r = 0; r < ROWS_PER_SLICE; r++) {
            const bool second = ((row0 + r) / ROWS_PER_CH) != ch0;
            const float sc = second ? sc1 : sc0;
            const float sh = second ? sh1 : sh0;
            uint4 v = sbuf[r * (ROW_ELEMS / 8) + tid];
            uint4 o;
            o.x = norm2(v.x, sc, sh);
            o.y = norm2(v.y, sc, sh);
            o.z = norm2(v.z, sc, sh);
            o.w = norm2(v.w, sc, sh);
            dst[r * (ROW_ELEMS / 8) + tid] = o;
        }
        __syncthreads();
        if (tid == 0 && w + STAGES < WAVES) issue_load(w + STAGES);
    }
}

}

extern "C" void kernel_launch(void* const* d_in, const int* in_sizes, int n_in,
                              void* d_out, int out_size) {
    const __nv_bfloat16* x = (const __nv_bfloat16*)d_in[0];
    const __nv_bfloat16* g = (const __nv_bfloat16*)d_in[1];
    const __nv_bfloat16* b = (const __nv_bfloat16*)d_in[2];
    __nv_bfloat16* out = (__nv_bfloat16*)d_out;
    static bool attr_done = false;
    if (!attr_done) {
        cudaFuncSetAttribute(gn::groupnorm_kernel, cudaFuncAttributeMaxDynamicSharedMemorySize, gn::SMEM_BYTES);
        attr_done = true;
    }
    gn::groupnorm_kernel<<<gn::NCTA, gn::THREADS, gn::SMEM_BYTES>>>(x, g, b, out);
}
```
